```python
import torch

def _softmax(x, axis=-1):
    return torch.softmax(x, dim=axis)
def _gelu(x):
    return torch.nn.functional.gelu(x, approximate="tanh")
def _silu(x):
    return torch.nn.functional.silu(x)
def _sigmoid(x):
    return torch.sigmoid(x)
def _layernorm(x, axis=-1, eps=1e-5):
    m = x.mean(dim=axis, keepdim=True)
    v = x.var(dim=axis, keepdim=True, unbiased=False)
    return (x - m) / torch.sqrt(v + eps)
def _scatter_add(tgt, idx, src, axis=0):
    return tgt.clone().index_add_(axis, idx, src)
def _segment_sum(src, seg, n):
    out = torch.zeros((n,) + src.shape[1:], dtype=src.dtype)
    return out.index_add_(0, seg, src)
def _pad(x, pw):
    flat = tuple(v for pair in reversed(pw) for v in pair)
    return torch.nn.functional.pad(x, flat)

kernel_name = 'gather_scatter__edge_featured_mpnn_gatedgcn__graph'

def setup_inputs():

    _w = (lambda a: (lambda t: t.to(torch.bfloat16) if t.is_floating_point() else t)(torch.as_tensor(a)))
    N, deg, D, De = 10000, 32, 128, max(0, 1)
    E = N * deg
    return {
        "x": _w((lambda *s: torch.randn(*s, dtype=torch.bfloat16) * 0.4)(N, D)),
        "e_attr": _w((lambda *s: torch.randn(*s, dtype=torch.bfloat16) * 1.6)(E, De)),
        "src": _w((lambda lo, hi, *s: torch.randint(lo, hi, s))(0, N, E).to(torch.int64)),
        "dst": _w((lambda lo, hi, *s: torch.randint(lo, hi, s))(0, N, E).to(torch.int64)),
        "w_a": _w((lambda *s: torch.randn(*s, dtype=torch.bfloat16) * 0.4)(D, D)),
        "w_b": _w((lambda *s: torch.randn(*s, dtype=torch.bfloat16) * 0.4)(D, D)),
        "w_c": _w((lambda *s: torch.randn(*s, dtype=torch.bfloat16) * 1.6)(De, D)),
        "w_u": _w((lambda *s: torch.randn(*s, dtype=torch.bfloat16) * 0.05)(D, D)),
        "w_v": _w((lambda *s: torch.randn(*s, dtype=torch.bfloat16) * 0.05)(D, D)),
    }

def reference(x, e_attr, src, dst, w_a, w_b, w_c, w_u, w_v):
    N, D = x.shape
    hv = x @ w_v
    g = x[dst] @ w_a + x[src] @ w_b + e_attr @ w_c
    eta = _sigmoid(g)
    denom = _segment_sum(eta, dst, N) + 1e-6
    eta_n = eta / denom[dst]
    agg = _segment_sum(eta_n * hv[src], dst, N)
    z = x @ w_u + agg
    relu_z = torch.where(z > 0, z, 0 * z)
    return x + relu_z
```

```cpp
#include <cuda_runtime.h>
#include <cuda_bf16.h>
#include <stdint.h>

#define DD 128
#define NPART 132
#define MAXNPP 80
#define MAXN (NPART * MAXNPP)
#define EPB_MAX 2560
#define OFFS_STRIDE 136
#define THREADS 512
#define NWARPS 16

__device__ uint4 g_bv[(MAXN + 1) * 32];
__device__ uint2 g_rec[NPART * EPB_MAX];
__device__ unsigned short g_off[NPART * OFFS_STRIDE];
__device__ unsigned int g_bar[4];

__device__ __forceinline__ uint32_t smem_u32(const void* p) {
    return (uint32_t)__cvta_generic_to_shared(p);
}
__device__ __forceinline__ void cp_async16(uint32_t dst, const void* src, int src_bytes) {
    asm volatile("cp.async.cg.shared.global [%0], [%1], 16, %2;\n" ::"r"(dst), "l"(src), "r"(src_bytes));
}
__device__ __forceinline__ void ldmatrix_x4(uint32_t& r0, uint32_t& r1, uint32_t& r2, uint32_t& r3, uint32_t addr) {
    asm volatile("ldmatrix.sync.aligned.m8n8.x4.shared.b16 {%0,%1,%2,%3}, [%4];\n"
                 : "=r"(r0), "=r"(r1), "=r"(r2), "=r"(r3) : "r"(addr));
}
__device__ __forceinline__ void ldmatrix_x4_trans(uint32_t& r0, uint32_t& r1, uint32_t& r2, uint32_t& r3, uint32_t addr) {
    asm volatile("ldmatrix.sync.aligned.m8n8.x4.trans.shared.b16 {%0,%1,%2,%3}, [%4];\n"
                 : "=r"(r0), "=r"(r1), "=r"(r2), "=r"(r3) : "r"(addr));
}
__device__ __forceinline__ void mma_bf16(float* c, uint32_t a0, uint32_t a1, uint32_t a2, uint32_t a3, uint32_t b0, uint32_t b1) {
    asm volatile("mma.sync.aligned.m16n8k16.row.col.f32.bf16.bf16.f32 {%0,%1,%2,%3}, {%4,%5,%6,%7}, {%8,%9}, {%0,%1,%2,%3};\n"
                 : "+f"(c[0]), "+f"(c[1]), "+f"(c[2]), "+f"(c[3])
                 : "r"(a0), "r"(a1), "r"(a2), "r"(a3), "r"(b0), "r"(b1));
}
__device__ __forceinline__ uint32_t pack_bf16(float lo, float hi) {
    __nv_bfloat162 v = __floats2bfloat162_rn(lo, hi);
    return *reinterpret_cast<uint32_t*>(&v);
}
__device__ __forceinline__ float bf_lo(uint32_t v) { return __uint_as_float(v << 16); }
__device__ __forceinline__ float bf_hi(uint32_t v) { return __uint_as_float(v & 0xffff0000u); }
__device__ __forceinline__ float ex2f(float x) {
    float y;
    asm("ex2.approx.ftz.f32 %0, %1;" : "=f"(y) : "f"(x));
    return y;
}
__device__ __forceinline__ float rcpf(float x) {
    float y;
    asm("rcp.approx.ftz.f32 %0, %1;" : "=f"(y) : "f"(x));
    return y;
}
__device__ __forceinline__ unsigned int ld_acquire(const unsigned int* p) {
    unsigned int v;
    asm volatile("ld.acquire.gpu.global.u32 %0, [%1];" : "=r"(v) : "l"(p) : "memory");
    return v;
}
__device__ __forceinline__ void grid_arrive(int idx) {
    __syncthreads();
    if (threadIdx.x == 0) { __threadfence(); atomicAdd(&g_bar[idx], 1u); }
}
__device__ __forceinline__ void grid_wait(int idx) {
    if (threadIdx.x == 0) {
        int it = 0;
        while (ld_acquire(&g_bar[idx]) < (unsigned)gridDim.x && ++it < (1 << 22)) __nanosleep(32);
    }
    __syncthreads();
}

#define RPT 9
#define CH (THREADS * RPT)
#define NSLOT (NWARPS * RPT)
#define SORT_CAP (CH + 4 * MAXNPP)
#define NLOG2E (-1.4426950408889634f)

#define SM_AU 0
#define SM_X (SM_AU + MAXNPP * 512)
#define SM_Q (SM_X + MAXNPP * 256)
#define SM_ACC SM_Q
#define SM_SOFF (SM_ACC + MAXNPP * 1024)
#define SM_SEV (SM_SOFF + SORT_CAP * 4)
#define SM_OWN (SM_SEV + SORT_CAP * 4)
#define SM_STAGE (SM_Q + 131072)
#define SM_HIST (SM_STAGE + EPB_MAX * 8)
#define SM_OFFS (SM_HIST + OFFS_STRIDE * 4)
#define SM_RUNS (SM_OFFS + OFFS_STRIDE * 4)
#define SM_RUNB (SM_RUNS + NSLOT * 4)
#define SM_NCNT (SM_RUNB + NSLOT * 4)
#define SM_NSTART (SM_NCNT + MAXNPP * 4)
#define SM_WSUM (SM_NSTART + (MAXNPP + 4) * 4)
#define SM_TOTAL (SM_WSUM + 128)
static_assert(SM_OWN + CH * 2 <= SM_STAGE, "phase 2 arrays must fit in the W region");
static_assert(SM_TOTAL <= 227 * 1024, "smem");
static_assert(2 * NWARPS <= MAXNPP && MAXNPP <= OFFS_STRIDE, "slots");

struct Params {
    const __nv_bfloat16* x;
    const __nv_bfloat16* e_attr;
    const int* src;
    const int* dst;
    const __nv_bfloat16* w0;
    const __nv_bfloat16* w1;
    const __nv_bfloat16* w2;
    const __nv_bfloat16* w3;
    const __nv_bfloat16* w_c;
    __nv_bfloat16* out;
    int N, E;
    int npp;
    int epb;
    uint32_t npp_magic;
    uint32_t zmask;
};

__device__ __forceinline__ void edge_accum2(const uint4 bv0, const float e0, const uint4 bv1, const float e1,
                                            const float* a, const float* wc, float* num, float* den) {
    const float b0[4] = {bf_lo(bv0.x), bf_hi(bv0.x), bf_lo(bv0.y), bf_hi(bv0.y)};
    const float v0[4] = {bf_lo(bv0.z), bf_hi(bv0.z), bf_lo(bv0.w), bf_hi(bv0.w)};
    const float b1[4] = {bf_lo(bv1.x), bf_hi(bv1.x), bf_lo(bv1.y), bf_hi(bv1.y)};
    const float v1[4] = {bf_lo(bv1.z), bf_hi(bv1.z), bf_lo(bv1.w), bf_hi(bv1.w)};
#pragma unroll
    for (int i = 0; i < 4; i++) {
        float t0 = fmaf(b0[i], NLOG2E, fmaf(e0, wc[i], a[i]));
        float t1 = fmaf(b1[i], NLOG2E, fmaf(e1, wc[i], a[i]));
        float d0 = 1.0f + ex2f(fminf(t0, 60.f));
        float d1 = 1.0f + ex2f(fminf(t1, 60.f));
        float r = rcpf(d0 * d1);
        float q = fmaf(d0, v1[i], d1 * v0[i]);
        num[i] = fmaf(r, q, num[i]);
        den[i] = fmaf(r, d0 + d1, den[i]);
    }
}

__device__ __forceinline__ uint4 ldg_idx(const uint4* base, uint32_t idx) {
    uint4 v;
    asm("{ .reg .u64 a; mad.wide.u32 a, %4, 16, %5; ld.global.nc.v4.u32 {%0,%1,%2,%3}, [a]; }"
        : "=r"(v.x), "=r"(v.y), "=r"(v.z), "=r"(v.w) : "r"(idx), "l"(base));
    return v;
}
__device__ __forceinline__ void prefetch_group(uint4 (&buf)[4], uint32_t& key, const uint4* soff4, int gi,
                                               const uint4* bvl) {
    const uint4 o = soff4[gi];
    key = o.x >> 21;
    buf[0] = ldg_idx(bvl, o.x & 0x1fffffu);
    buf[1] = ldg_idx(bvl, o.y);
    buf[2] = ldg_idx(bvl, o.z);
    buf[3] = ldg_idx(bvl, o.w);
}

__global__ void __launch_bounds__(THREADS, 1) gatedgcn_fused(const Params p) {
    extern __shared__ __align__(128) unsigned char smem_raw[];
    uint4* au_s = reinterpret_cast<uint4*>(smem_raw + SM_AU);
    unsigned char* x_s = smem_raw + SM_X;
    unsigned char* w_s = smem_raw + SM_Q;
    float* accum = reinterpret_cast<float*>(smem_raw + SM_ACC);
    uint32_t* soff = reinterpret_cast<uint32_t*>(smem_raw + SM_SOFF);
    uint32_t* sev = reinterpret_cast<uint32_t*>(smem_raw + SM_SEV);
    unsigned short* owner = reinterpret_cast<unsigned short*>(smem_raw + SM_OWN);
    uint2* stage = reinterpret_cast<uint2*>(smem_raw + SM_STAGE);
    int* hist = reinterpret_cast<int*>(smem_raw + SM_HIST);
    int* offs = reinterpret_cast<int*>(smem_raw + SM_OFFS);
    int* run_start = reinterpret_cast<int*>(smem_raw + SM_RUNS);
    int* run_base = reinterpret_cast<int*>(smem_raw + SM_RUNB);
    int* node_cnt = reinterpret_cast<int*>(smem_raw + SM_NCNT);
    int* node_start = reinterpret_cast<int*>(smem_raw + SM_NSTART);
    int* wsum = reinterpret_cast<int*>(smem_raw + SM_WSUM);
    int* stag = hist;
    int* done = offs;

    const int tid = threadIdx.x, lane = tid & 31, warp = tid >> 5;
    const int part = blockIdx.x;
    const int npp = p.npp;
    const int n0 = part * npp;
    const int nn = max(0, min(npp, p.N - n0));

    if (tid < OFFS_STRIDE) hist[tid] = 0;
    if (tid < MAXNPP) node_cnt[tid] = 0;
    if (tid == 0) { wsum[31] = 0; wsum[30] = 0; }
    if (tid >= NPART && tid < NSLOT) run_start[tid] = 0;
    int4 rs[2], rd[2];
    uint2 re[2];
    const int ebase = part * p.epb;
    const int eend = min(p.E, ebase + p.epb);
#pragma unroll
    for (int c = 0; c < 2; c++) {
        const int e0 = ebase + (c * THREADS + tid) * 4;
        rs[c] = make_int4(0, 0, 0, 0); rd[c] = make_int4(-1, -1, -1, -1); re[c] = make_uint2(0u, 0u);
        if (e0 + 3 < eend) {
            rs[c] = __ldg(reinterpret_cast<const int4*>(p.src + e0));
            rd[c] = __ldg(reinterpret_cast<const int4*>(p.dst + e0));
            re[c] = __ldg(reinterpret_cast<const uint2*>(p.e_attr + e0));
        }
    }
    {
        const uint32_t xs_base = smem_u32(x_s);
        for (int c = tid; c < MAXNPP * 16; c += THREADS) {
            int r = c >> 4, cc = c & 15;
            int ok = r < nn;
            const __nv_bfloat16* src = p.x + (size_t)(ok ? n0 + r : 0) * DD + cc * 8;
            cp_async16(xs_base + r * 256 + ((cc ^ (r & 7)) << 4), src, ok ? 16 : 0);
        }
        const uint32_t ws_base = smem_u32(w_s);
        {
            const int k0 = tid >> 4, cc = tid & 15;
            const uint32_t dst0 = ws_base + k0 * 1024;
            const uint32_t sw = (uint32_t)(k0 & 7);
            const int soff0 = k0 * DD + cc * 8;
#pragma unroll
            for (int it = 0; it < 4; it++) {
                cp_async16(dst0 + it * 32768 + (((uint32_t)cc ^ sw) << 4), p.w0 + soff0 + it * 32 * DD, 16);
                cp_async16(dst0 + it * 32768 + (((uint32_t)(16 + cc) ^ sw) << 4), p.w1 + soff0 + it * 32 * DD, 16);
                cp_async16(dst0 + it * 32768 + (((uint32_t)(32 + cc) ^ sw) << 4), p.w2 + soff0 + it * 32 * DD, 16);
                cp_async16(dst0 + it * 32768 + (((uint32_t)(48 + cc) ^ sw) << 4), p.w3 + soff0 + it * 32 * DD, 16);
            }
        }
        asm volatile("cp.async.commit_group;\n");
    }
    __syncthreads();
    int es[8], ed[8];
    uint32_t ee[8];
#pragma unroll
    for (int c = 0; c < 2; c++) {
        es[4 * c] = rs[c].x; es[4 * c + 1] = rs[c].y; es[4 * c + 2] = rs[c].z; es[4 * c + 3] = rs[c].w;
        ed[4 * c] = rd[c].x; ed[4 * c + 1] = rd[c].y; ed[4 * c + 2] = rd[c].z; ed[4 * c + 3] = rd[c].w;
        ee[4 * c] = re[c].x << 16; ee[4 * c + 1] = re[c].x & 0xffff0000u; ee[4 * c + 2] = re[c].y << 16; ee[4 * c + 3] = re[c].y & 0xffff0000u;
        const int e0 = ebase + (c * THREADS + tid) * 4;
        if (e0 < eend && e0 + 3 >= eend) {
#pragma unroll
            for (int i = 0; i < 4; i++) {
                if (e0 + i < eend) {
                    es[4 * c + i] = p.src[e0 + i]; ed[4 * c + i] = p.dst[e0 + i];
                    ee[4 * c + i] = (uint32_t)__bfloat16_as_ushort(p.e_attr[e0 + i]) << 16;
                }
            }
        }
    }

    {
        int pt[8], rk[8];
#pragma unroll
        for (int i = 0; i < 8; i++) {
            pt[i] = 0; rk[i] = 0;
            if (ed[i] >= 0) { pt[i] = (int)__umulhi((uint32_t)ed[i], p.npp_magic); rk[i] = atomicAdd(&hist[pt[i]], 1); }
        }
        __syncthreads();
        if (warp == 0) {
            int v[5], sum = 0;
#pragma unroll
            for (int i = 0; i < 5; i++) { int idx = lane * 5 + i; v[i] = idx < NPART ? hist[idx] : 0; sum += v[i]; }
            int inc = sum;
#pragma unroll
            for (int o = 1; o < 32; o <<= 1) { int t = __shfl_up_sync(0xffffffffu, inc, o); if (lane >= o) inc += t; }
            int run = inc - sum;
#pragma unroll
            for (int i = 0; i < 5; i++) { int idx = lane * 5 + i; if (idx <= NPART) offs[idx] = run; run += v[i]; }
        }
        __syncthreads();
#pragma unroll
        for (int i = 0; i < 8; i++) {
            if (ed[i] >= 0) stage[offs[pt[i]] + rk[i]] = make_uint2(ee[i] | (uint32_t)es[i], (uint32_t)(ed[i] - pt[i] * npp));
        }
        __syncthreads();
        const int cnt4 = (offs[NPART] + 1) >> 1;
        const uint4* st4 = reinterpret_cast<const uint4*>(stage);
        uint4* g4 = reinterpret_cast<uint4*>(g_rec + (size_t)part * EPB_MAX);
        for (int c = tid; c < cnt4; c += THREADS) g4[c] = st4[c];
        if (tid <= NPART) g_off[part * OFFS_STRIDE + tid] = (unsigned short)offs[tid];
    }
    asm volatile("cp.async.wait_group 0;\n");
    grid_arrive(0);

    int len = 0, o0 = 0, my_start = 0;
    {
        const int pairw = warp >> 3, kk = warp & 7, hi = lane >> 4;
        float acc[5][4][4];
#pragma unroll
        for (int m = 0; m < 5; m++)
#pragma unroll
            for (int t = 0; t < 4; t++) { acc[m][t][0] = acc[m][t][1] = acc[m][t][2] = acc[m][t][3] = 0.f; }
        const uint32_t a_base = smem_u32(x_s) + (lane & 15) * 256;
        const uint32_t b_base = smem_u32(w_s) + (lane & 15) * 1024;
        const uint32_t bc0 = (uint32_t)(((pairw * 32 + 2 * kk + hi) ^ (lane & 7)) << 4);
        const uint32_t bc1 = (uint32_t)(((pairw * 32 + 16 + 2 * kk + hi) ^ (lane & 7)) << 4);
#pragma unroll
        for (int ks = 0; ks < 8; ks++) {
            uint32_t b0, b1, b2, b3, c0, c1, c2, c3;
            ldmatrix_x4_trans(b0, b1, b2, b3, b_base + ks * 16 * 1024 + bc0);
            ldmatrix_x4_trans(c0, c1, c2, c3, b_base + ks * 16 * 1024 + bc1);
#pragma unroll
            for (int m = 0; m < 5; m++) {
                uint32_t a0, a1, a2, a3;
                ldmatrix_x4(a0, a1, a2, a3, a_base + m * 16 * 256 + (((ks * 2 + hi) ^ (lane & 7)) << 4));
                mma_bf16(acc[m][0], a0, a1, a2, a3, b0, b1);
                mma_bf16(acc[m][1], a0, a1, a2, a3, b2, b3);
                mma_bf16(acc[m][2], a0, a1, a2, a3, c0, c1);
                mma_bf16(acc[m][3], a0, a1, a2, a3, c2, c3);
            }
        }
        if (tid < NPART) {
            int it = 0;
            while (ld_acquire(&g_bar[0]) < (unsigned)gridDim.x && ++it < (1 << 22)) __nanosleep(32);
            o0 = __ldcg(&g_off[tid * OFFS_STRIDE + part]);
            len = (int)__ldcg(&g_off[tid * OFFS_STRIDE + part + 1]);
        }
        const int l = 4 * kk + (lane & 3);
#pragma unroll
        for (int m = 0; m < 5; m++) {
            const int r = m * 16 + (lane >> 2);
            uint4 v0, v1;
            v0.x = pack_bf16(acc[m][0][0], acc[m][0][1]); v0.y = pack_bf16(acc[m][1][0], acc[m][1][1]);
            v0.z = pack_bf16(acc[m][2][0], acc[m][2][1]); v0.w = pack_bf16(acc[m][3][0], acc[m][3][1]);
            v1.x = pack_bf16(acc[m][0][2], acc[m][0][3]); v1.y = pack_bf16(acc[m][1][2], acc[m][1][3]);
            v1.z = pack_bf16(acc[m][2][2], acc[m][2][3]); v1.w = pack_bf16(acc[m][3][2], acc[m][3][3]);
            if (pairw == 0) {
                au_s[r * 32 + l] = v0;
                au_s[(r + 8) * 32 + l] = v1;
            } else {
                if (r < nn) g_bv[(size_t)(n0 + r) * 32 + l] = v0;
                if (r + 8 < nn) g_bv[(size_t)(n0 + r + 8) * 32 + l] = v1;
            }
        }
    }
    if (part == 0 && warp == 0) g_bv[MAXN * 32 + lane] = make_uint4(0xff7fff7fu, 0xff7fff7fu, 0u, 0u);
    if (tid < NPART) {
        len -= o0;
        run_start[tid] = min(len, 32);
        run_base[tid] = tid * EPB_MAX + o0;
        if (len > 32) {
            int idx = NPART + atomicAdd(&wsum[30], 1);
            if (len > 64 || idx >= NSLOT) wsum[31] = 1;
            else { run_start[idx] = len - 32; run_base[idx] = tid * EPB_MAX + o0 + 32; }
        }
    }
    if (tid >= THREADS - 128) {
        const int t = tid - (THREADS - 128);
        if (t < 2 * NWARPS) stag[t] = -1;
        if (t < MAXNPP) done[t] = 0;
    }
    grid_arrive(1);

    const int fw = (lane >> 2) * 8 + (lane & 3);
    const uint2 wc2 = make_uint2(reinterpret_cast<const uint32_t*>(p.w_c)[fw], reinterpret_cast<const uint32_t*>(p.w_c)[fw + 4]);
    const uint4* bvl = g_bv + lane;
    const uint32_t zmask = p.zmask;
    const bool fast = (wsum[31] == 0);
    int total = 1;
    if (!fast) {
        __syncthreads();
        int inc = len;
#pragma unroll
        for (int o = 1; o < 32; o <<= 1) { int t = __shfl_up_sync(0xffffffffu, inc, o); if (lane >= o) inc += t; }
        if (lane == 31) wsum[warp] = inc;
        __syncthreads();
        int pre = 0;
        for (int w = 0; w < warp; w++) pre += wsum[w];
        my_start = pre + inc - len;
        if (tid <= NPART) run_start[tid] = my_start;
        if (tid < NPART) run_base[tid] = tid * EPB_MAX + o0 - my_start;
        __syncthreads();
        total = run_start[NPART];
    }
    bool bv_ready = false;
    const bool single = total <= CH;
    auto emit = [&](const int j, const float* nu, const float* de) {
        const uint2 uu = *reinterpret_cast<const uint2*>(reinterpret_cast<const uint32_t*>(au_s + j * 32 + lane) + 2);
        const int kk = lane >> 2, q = lane & 3;
        const uint32_t xa = *reinterpret_cast<const uint32_t*>(x_s + j * 256 + (((2 * kk) ^ (j & 7)) << 4) + q * 4);
        const uint32_t xb = *reinterpret_cast<const uint32_t*>(x_s + j * 256 + (((2 * kk + 1) ^ (j & 7)) << 4) + q * 4);
        const float u[4] = {bf_lo(uu.x), bf_hi(uu.x), bf_lo(uu.y), bf_hi(uu.y)};
        const float xv[4] = {bf_lo(xa), bf_hi(xa), bf_lo(xb), bf_hi(xb)};
        float o[4];
#pragma unroll
        for (int i = 0; i < 4; i++) {
            float agg = __fdividef(nu[i], de[i] + 1e-6f);
            float z = u[i] + agg;
            o[i] = xv[i] + (z > 0.f ? z : 0.f * z);
        }
        uint32_t* orow = reinterpret_cast<uint32_t*>(p.out + (size_t)(n0 + j) * DD);
        orow[fw] = pack_bf16(o[0], o[1]);
        orow[fw + 4] = pack_bf16(o[2], o[3]);
    };
    const float wc[4] = {NLOG2E * bf_lo(wc2.x), NLOG2E * bf_hi(wc2.x), NLOG2E * bf_lo(wc2.y), NLOG2E * bf_hi(wc2.y)};

    for (int c0 = 0; c0 < total; c0 += CH) {
        uint2 rec[RPT];
        int rank[RPT];
        if (fast) {
#pragma unroll
            for (int k = 0; k < RPT; k++) {
                const int run = warp + k * NWARPS;
                rec[k] = make_uint2(0u, 0xffffffffu);
                if (lane < run_start[run]) rec[k] = __ldcg(&g_rec[run_base[run] + lane]);
            }
        } else {
            const int clen = min(CH, total - c0);
            if (tid < MAXNPP) node_cnt[tid] = 0;
            {
                int lo = max(my_start, c0), hi = min(my_start + len, c0 + clen);
                for (int i = lo; i < hi; i++) owner[i - c0] = (unsigned short)tid;
            }
            __syncthreads();
#pragma unroll
            for (int k = 0; k < RPT; k++) {
                int i = k * THREADS + tid;
                rec[k] = make_uint2(0u, 0xffffffffu);
                if (i < clen) rec[k] = __ldcg(&g_rec[run_base[owner[i]] + c0 + i]);
            }
        }
        if (c0 == 0 && !single) {
            float4* a4 = reinterpret_cast<float4*>(accum);
            for (int c = tid; c < nn * 64; c += THREADS) a4[c] = make_float4(0.f, 0.f, 0.f, 0.f);
        }
#pragma unroll
        for (int k = 0; k < RPT; k++) {
            rank[k] = 0;
            if (rec[k].y != 0xffffffffu) rank[k] = atomicAdd(&node_cnt[rec[k].y], 1);
        }
        __syncthreads();
        if (warp == 0) {
            int v[3], sum = 0;
#pragma unroll
            for (int i = 0; i < 3; i++) { int idx = lane * 3 + i; v[i] = idx < MAXNPP ? ((node_cnt[idx] + 3) & ~3) : 0; sum += v[i]; }
            int inc = sum;
#pragma unroll
            for (int o = 1; o < 32; o <<= 1) { int t = __shfl_up_sync(0xffffffffu, inc, o); if (lane >= o) inc += t; }
            int run = inc - sum;
#pragma unroll
            for (int i = 0; i < 3; i++) { int idx = lane * 3 + i; if (idx <= MAXNPP) node_start[idx] = run; run += v[i]; }
        }
        __syncthreads();
        if (!bv_ready && tid == THREADS - 1) {
            int it = 0;
            while (ld_acquire(&g_bar[1]) < (unsigned)gridDim.x && ++it < (1 << 22)) __nanosleep(32);
        }
#pragma unroll
        for (int k = 0; k < RPT; k++) {
            if (rec[k].y != 0xffffffffu) {
                const int nd = rec[k].y;
                uint32_t off = (rec[k].x & 0xffffu) * 32u;
                if ((rank[k] & 3) == 0) off |= (uint32_t)nd << 21;
                const int pos = node_start[nd] + rank[k];
                soff[pos] = off;
                sev[pos] = rec[k].x & 0xffff0000u;
            }
        }
        if (tid < MAXNPP) {
            int c = node_cnt[tid], st = node_start[tid];
            for (int j = c; j & 3; j++) { soff[st + j] = MAXN * 32u; sev[st + j] = 0u; }
        }
        bv_ready = true;
        __syncthreads();

        const uint4* soff4 = reinterpret_cast<const uint4*>(soff);
        const uint4* sev4 = reinterpret_cast<const uint4*>(sev);
        if (!single) {
            for (int j = warp; j < nn; j += NWARPS) {
                float a[4], num[4] = {0.f, 0.f, 0.f, 0.f}, den[4] = {0.f, 0.f, 0.f, 0.f};
                const uint2 au = *reinterpret_cast<const uint2*>(au_s + j * 32 + lane);
                a[0] = NLOG2E * bf_lo(au.x); a[1] = NLOG2E * bf_hi(au.x); a[2] = NLOG2E * bf_lo(au.y); a[3] = NLOG2E * bf_hi(au.y);
                const int ge = node_start[j + 1] >> 2;
                for (int g = node_start[j] >> 2; g < ge; g++) {
                    uint4 buf[4];
                    uint32_t key;
                    prefetch_group(buf, key, soff4, g, bvl);
                    const uint4 ev = sev4[g];
                    edge_accum2(buf[0], __uint_as_float(ev.x), buf[1], __uint_as_float(ev.y), a, wc, num, den);
                    edge_accum2(buf[2], __uint_as_float(ev.z), buf[3], __uint_as_float(ev.w), a, wc, num, den);
                }
                float* acc_n = accum + j * 256 + lane * 4;
#pragma unroll
                for (int i = 0; i < 4; i++) { acc_n[i] += num[i]; acc_n[128 + i] += den[i]; }
            }
            __syncthreads();
            continue;
        }
        const int G = node_start[MAXNPP] >> 2;
        const int g0 = (G * warp) / NWARPS;
        const int g1 = (G * (warp + 1)) / NWARPS;
        if (g0 < g1) {
            uint4 bufA0[4], bufA1[4], bufB0[4], bufB1[4];
            uint32_t kA0, kA1 = 0, kB0 = 0, kB1 = 0;
            bufA1[3].w = 0; bufB1[3].w = 0; bufB0[3].w = 0;
            prefetch_group(bufA0, kA0, soff4, g0, bvl);
            if (g0 + 1 < g1) prefetch_group(bufA1, kA1, soff4, g0 + 1, bvl);
            uint32_t cur = kA0;
            float a[4], num[4] = {0.f, 0.f, 0.f, 0.f}, den[4] = {0.f, 0.f, 0.f, 0.f};
            {
                const uint2 au = *reinterpret_cast<const uint2*>(au_s + cur * 32 + lane);
                a[0] = NLOG2E * bf_lo(au.x); a[1] = NLOG2E * bf_hi(au.x); a[2] = NLOG2E * bf_lo(au.y); a[3] = NLOG2E * bf_hi(au.y);
            }
            bool split = (node_start[cur] >> 2) < g0;
            auto finish = [&]() {
                if (split) {
                    const int nb = node_start[cur] >> 2, ne = node_start[cur + 1] >> 2;
                    const int slot = 2 * warp + (nb < g0 ? 0 : 1);
                    float* sp = accum + slot * 256 + lane * 4;
                    *reinterpret_cast<float4*>(sp) = make_float4(num[0], num[1], num[2], num[3]);
                    *reinterpret_cast<float4*>(sp + 128) = make_float4(den[0], den[1], den[2], den[3]);
                    if (lane == 0) stag[slot] = (int)cur;
                    __threadfence_block();
                    __syncwarp();
                    const int cnt = min(ne, g1) - max(nb, g0);
                    int old = 0;
                    if (lane == 0) old = atomicAdd(&done[cur], cnt);
                    old = __shfl_sync(0xffffffffu, old, 0);
                    split = false;
                    if (old + cnt != ne - nb) return;
                    __threadfence_block();
                    unsigned int cm = __ballot_sync(0xffffffffu, *(volatile int*)&stag[lane] == (int)cur) & ~(1u << slot);
                    while (cm) {
                        const int w = __ffs(cm) - 1;
                        cm &= cm - 1;
                        const float4 cn = *reinterpret_cast<const float4*>(accum + w * 256 + lane * 4);
                        const float4 cd = *reinterpret_cast<const float4*>(accum + w * 256 + 128 + lane * 4);
                        num[0] += cn.x; num[1] += cn.y; num[2] += cn.z; num[3] += cn.w;
                        den[0] += cd.x; den[1] += cd.y; den[2] += cd.z; den[3] += cd.w;
                    }
                }
                emit((int)cur, num, den);
            };
            auto step = [&](const uint4 (&buf)[4], const uint32_t key, const int gi) {
                const uint4 ev = sev4[gi];
                if (key != cur) {
                    finish();
                    cur = key;
                    const uint2 au = *reinterpret_cast<const uint2*>(au_s + cur * 32 + lane);
                    a[0] = NLOG2E * bf_lo(au.x); a[1] = NLOG2E * bf_hi(au.x); a[2] = NLOG2E * bf_lo(au.y); a[3] = NLOG2E * bf_hi(au.y);
#pragma unroll
                    for (int i = 0; i < 4; i++) { num[i] = 0.f; den[i] = 0.f; }
                }
                edge_accum2(buf[0], __uint_as_float(ev.x), buf[1], __uint_as_float(ev.y), a, wc, num, den);
                edge_accum2(buf[2], __uint_as_float(ev.z), buf[3], __uint_as_float(ev.w), a, wc, num, den);
            };
            int g = g0;
            while (true) {
                {
                    const uint4* bd = bvl + ((bufA0[3].w ^ bufA1[3].w) & zmask);
                    if (g + 2 < g1) prefetch_group(bufB0, kB0, soff4, g + 2, bd);
                    if (g + 3 < g1) prefetch_group(bufB1, kB1, soff4, g + 3, bd);
                }
                step(bufA0, kA0, g);
                if (g + 1 >= g1) break;
                step(bufA1, kA1, g + 1);
                if (g + 2 >= g1) break;
                {
                    const uint4* bd = bvl + ((bufB0[3].w ^ bufB1[3].w) & zmask);
                    if (g + 4 < g1) prefetch_group(bufA0, kA0, soff4, g + 4, bd);
                    if (g + 5 < g1) prefetch_group(bufA1, kA1, soff4, g + 5, bd);
                }
                step(bufB0, kB0, g + 2);
                if (g + 3 >= g1) break;
                step(bufB1, kB1, g + 3);
                if (g + 4 >= g1) break;
                g += 4;
            }
            split = split || (node_start[cur + 1] >> 2) > g1;
            finish();
        }
        for (int j = warp; j < nn; j += NWARPS) {
            if (node_cnt[j] == 0) {
                const float zz[4] = {0.f, 0.f, 0.f, 0.f};
                emit(j, zz, zz);
            }
        }
    }
    if (!single) {
        if (!bv_ready) {
            grid_wait(1);
        }
        for (int j = warp; j < nn; j += NWARPS) {
            const float4 n4 = *reinterpret_cast<const float4*>(accum + j * 256 + lane * 4);
            const float4 d4 = *reinterpret_cast<const float4*>(accum + j * 256 + 128 + lane * 4);
            const float nu[4] = {n4.x, n4.y, n4.z, n4.w}, de[4] = {d4.x, d4.y, d4.z, d4.w};
            emit(j, nu, de);
        }
    } else if (!bv_ready) {
        grid_wait(1);
        for (int j = warp; j < nn; j += NWARPS) {
            const float zz[4] = {0.f, 0.f, 0.f, 0.f};
            emit(j, zz, zz);
        }
    }
    if (tid == 0) {
        unsigned int t = atomicAdd(&g_bar[2], 1u);
        if (t == gridDim.x - 1) { g_bar[0] = 0; g_bar[1] = 0; g_bar[2] = 0; }
    }
}

extern "C" void kernel_launch(void* const* d_in, const int* in_sizes, int n_in,
                              void* d_out, int out_size) {
    Params p;
    p.x = (const __nv_bfloat16*)d_in[0];
    p.e_attr = (const __nv_bfloat16*)d_in[1];
    p.src = (const int*)d_in[2];
    p.dst = (const int*)d_in[3];
    p.w0 = (const __nv_bfloat16*)d_in[4];
    p.w2 = (const __nv_bfloat16*)d_in[5];
    p.w_c = (const __nv_bfloat16*)d_in[6];
    p.w1 = (const __nv_bfloat16*)d_in[7];
    p.w3 = (const __nv_bfloat16*)d_in[8];
    p.out = (__nv_bfloat16*)d_out;
    p.N = in_sizes[0] / DD;
    p.E = in_sizes[2];
    p.npp = (p.N + NPART - 1) / NPART;
    p.epb = (((p.E + NPART - 1) / NPART) + 3) & ~3;
    p.npp_magic = (uint32_t)((1ull << 32) / (unsigned long long)p.npp) + 1u;
    p.zmask = 0u;

    static bool attr_done = false;
    if (!attr_done) {
        cudaFuncSetAttribute(gatedgcn_fused, cudaFuncAttributeMaxDynamicSharedMemorySize, SM_TOTAL);
        attr_done = true;
    }
    gatedgcn_fused<<<NPART, THREADS, SM_TOTAL>>>(p);
}
```
